```python
import torch

def _softmax(x, axis=-1):
    return torch.softmax(x, dim=axis)
def _gelu(x):
    return torch.nn.functional.gelu(x, approximate="tanh")
def _silu(x):
    return torch.nn.functional.silu(x)
def _sigmoid(x):
    return torch.sigmoid(x)
def _layernorm(x, axis=-1, eps=1e-5):
    m = x.mean(dim=axis, keepdim=True)
    v = x.var(dim=axis, keepdim=True, unbiased=False)
    return (x - m) / torch.sqrt(v + eps)
def _scatter_add(tgt, idx, src, axis=0):
    return tgt.clone().index_add_(axis, idx, src)
def _segment_sum(src, seg, n):
    out = torch.zeros((n,) + src.shape[1:], dtype=src.dtype)
    return out.index_add_(0, seg, src)
def _pad(x, pw):
    flat = tuple(v for pair in reversed(pw) for v in pair)
    return torch.nn.functional.pad(x, flat)

kernel_name = 'gated_mix__ssm_conv_s5__dense_activation_mish__prompt'

def setup_inputs():

    _w = (lambda a: (lambda t: t.to(torch.bfloat16) if t.is_floating_point() else t)(torch.as_tensor(a)))
    def _A_setup():
        B, S, D = 1, 2048, 512
        P = D
        Lambda_re = -0.5 * (lambda _x: torch.exp(torch.as_tensor(_x)))((lambda *s: torch.randn(*s, dtype=torch.bfloat16) * 0.2)(P))
        Lambda_im = (lambda *s: torch.randn(*s, dtype=torch.bfloat16) * 0.2)(P) * 1.0
        B_re = (lambda *s: torch.randn(*s, dtype=torch.bfloat16) * 0.2)(P, D) * (D ** -0.5)
        B_im = (lambda *s: torch.randn(*s, dtype=torch.bfloat16) * 0.2)(P, D) * (D ** -0.5)
        C_re = (lambda *s: torch.randn(*s, dtype=torch.bfloat16) * 0.2)(D, P) * (P ** -0.5)
        C_im = (lambda *s: torch.randn(*s, dtype=torch.bfloat16) * 0.2)(D, P) * (P ** -0.5)
        log_dt = (lambda *s: torch.randn(*s, dtype=torch.bfloat16) * 0.2)(P) * 0.3 - 2.0
        Dskip = (lambda *s: torch.randn(*s, dtype=torch.bfloat16) * 0.05)(D)
        return {
            "x": _w((lambda *s: torch.randn(*s, dtype=torch.bfloat16) * 0.05)(B, S, D)),
            "Lambda_re": _w(Lambda_re),
            "Lambda_im": _w(Lambda_im),
            "B_re": _w(B_re),
            "B_im": _w(B_im),
            "C_re": _w(C_re),
            "C_im": _w(C_im),
            "log_dt": _w(log_dt),
            "Dskip": _w(Dskip),
        }
    _A_in = _A_setup()

    def _B_setup():
        B, S, D, F = 1, 2048, 512, 1792
        return {
            "x": _w((lambda *s: torch.randn(*s, dtype=torch.bfloat16) * 0.05)(B, S, D)),
            "w1": _w((lambda *s: torch.randn(*s, dtype=torch.bfloat16) * 3.2)(D, F) * (D ** -0.5)),
            "b1": _w((lambda *s: torch.randn(*s, dtype=torch.bfloat16) * 0.05)(F)),
            "w2": _w((lambda *s: torch.randn(*s, dtype=torch.bfloat16) * 0.05)(F, D) * (F ** -0.5)),
        }
    _B_in = _B_setup()

    return {
        "A_x": _A_in["x"],
        "A_Lambda_re": _A_in["Lambda_re"],
        "A_Lambda_im": _A_in["Lambda_im"],
        "A_B_re": _A_in["B_re"],
        "A_B_im": _A_in["B_im"],
        "A_C_re": _A_in["C_re"],
        "A_C_im": _A_in["C_im"],
        "A_log_dt": _A_in["log_dt"],
        "A_Dskip": _A_in["Dskip"],
        "B_x": _B_in["x"],
        "B_w1": _B_in["w1"],
        "B_b1": _B_in["b1"],
        "B_w2": _B_in["w2"],
        "gate_w": _w((lambda *s: torch.randn(*s, dtype=torch.bfloat16) * 0.05)(512) * 16.0),
    }

def reference(A_x, A_Lambda_re, A_Lambda_im, A_B_re, A_B_im, A_C_re, A_C_im, A_log_dt, A_Dskip, B_x, B_w1, B_b1, B_w2, gate_w):
    def _A_ref(x, Lambda_re, Lambda_im, B_re, B_im, C_re, C_im, log_dt, Dskip):
        Bsz, L, H = x.shape
        Lam = Lambda_re + 1j * Lambda_im
        Bmat = B_re + 1j * B_im
        Cmat = C_re + 1j * C_im
        dt = torch.exp(log_dt)
        Lam_bar = torch.exp(dt * Lam)
        B_bar = ((Lam_bar - 1.0) / Lam)[:, None] * Bmat
        Bu = torch.einsum("bld,pd->blp", x + 0j, B_bar)
        h = torch.zeros_like(Bu[:, 0, :])
        hs = []
        for t in range(L):
            h = Lam_bar[None, :] * h + Bu[:, t, :]
            hs.append(h)
        hseq = torch.stack(hs, 1)
        y = 2.0 * torch.einsum("blp,dp->bld", hseq, Cmat).real + x * Dskip[None, None, :]
        return y

    def _B_ref(x, w1, b1, w2):
        h = torch.einsum("bsd,df->bsf", x, w1) + b1
        sp = torch.log1p(torch.exp(-torch.abs(h))) + torch.where(h > 0, h, torch.zeros_like(h))
        act = h * torch.tanh(sp)
        return torch.einsum("bsf,fd->bsd", act, w2)

    x = A_x
    g = _sigmoid((x * gate_w).sum(-1, keepdims=True))
    a = _A_ref(x, A_Lambda_re, A_Lambda_im, A_B_re, A_B_im, A_C_re, A_C_im, A_log_dt, A_Dskip)
    b = _B_ref(x, B_w1, B_b1, B_w2)
    return g * a + (1 - g) * b
```

```cpp
#include <cuda_runtime.h>
#include <cuda_bf16.h>
#include <cuda.h>
#include <stdint.h>

namespace {

constexpr int DM = 512, FF = 1792;
constexpr int NMT = 16, NFC = 8, NSLOT = 6;
constexpr uint32_t X_OFF    = 0;
constexpr uint32_t RING_OFF = 131072;
constexpr uint32_t BAR_OFF  = RING_OFF + NSLOT * 16384;
constexpr uint32_t DSK_OFF  = BAR_OFF + 368;
constexpr uint32_t BIAS_OFF = DSK_OFF + 128;
constexpr uint32_t GROW_OFF = BIAS_OFF + 928;
constexpr uint32_t SMEM_BYTES = GROW_OFF + 1024;
constexpr uint32_t XFULL = 0, FULL = 64, EMPTY = 112, HBAR = 160, GBAR = 168, RDY = 176, DBAR = 184, ZBAR = 248, LBAR = 256, XBAR = 264, DONE = 344, EPOCH = 352, HRDY = 360;
constexpr uint32_t HT_OFF = X_OFF + 2 * 16384, XB_OFF = X_OFF + 4 * 16384;
constexpr int SPIN_LIMIT = 1 << 20;
constexpr long long WATCHDOG_CLKS = 1ll << 33;

struct __align__(64) Maps { CUtensorMap x, b, w1a, w1b, w2a, w2b, cre, cim, y; };
struct Params {
  const __nv_bfloat16 *xp, *b0, *b1p, *lam_re, *lam_im, *log_dt, *dskip, *b1, *gate;
  int swapB;
};

__device__ uint4 g_part[NMT * NFC * 3 * 4 * 256];
__device__ uint2 g_agg[NMT * NFC * 64];
__device__ uint2 g_z[NMT * 64];
__device__ unsigned g_epoch[NMT * NFC];

template<int TB, uint32_t HB> __device__ __forceinline__ void wgmma_rs_n64(float (&d)[32], uint32_t a0, uint32_t a1, uint32_t a2, uint32_t a3, uint32_t db, int sc) {
  asm volatile("{\n.reg .pred p;\n.reg .b64 db;\nsetp.ne.b32 p, %37, 0;\nmov.b64 db, {%36, %39};\n"
    "wgmma.mma_async.sync.aligned.m64n64k16.f32.bf16.bf16 {%0, %1, %2, %3, %4, %5, %6, %7, %8, %9, %10, %11, %12, %13, %14, %15, %16, %17, %18, %19, %20, %21, %22, %23, %24, %25, %26, %27, %28, %29, %30, %31}, {%32,%33,%34,%35}, db, p, 1, 1, %38;\n}\n"
    : "+f"(d[0]), "+f"(d[1]), "+f"(d[2]), "+f"(d[3]), "+f"(d[4]), "+f"(d[5]), "+f"(d[6]), "+f"(d[7]), "+f"(d[8]), "+f"(d[9]), "+f"(d[10]), "+f"(d[11]), "+f"(d[12]), "+f"(d[13]), "+f"(d[14]), "+f"(d[15]), "+f"(d[16]), "+f"(d[17]), "+f"(d[18]), "+f"(d[19]), "+f"(d[20]), "+f"(d[21]), "+f"(d[22]), "+f"(d[23]), "+f"(d[24]), "+f"(d[25]), "+f"(d[26]), "+f"(d[27]), "+f"(d[28]), "+f"(d[29]), "+f"(d[30]), "+f"(d[31])
    : "r"(a0), "r"(a1), "r"(a2), "r"(a3), "r"(db), "r"(sc), "n"(TB), "n"(HB));
}
template<int TB, uint32_t HB> __device__ __forceinline__ void wgmma_rs3_n192(float (&d)[32], float (&e)[32], float (&f)[32], uint32_t a0, uint32_t a1, uint32_t a2, uint32_t a3, uint32_t db, int sc) {
  asm volatile("{\n.reg .pred p;\n.reg .b64 db;\nsetp.ne.b32 p, %101, 0;\nmov.b64 db, {%100, %103};\n"
    "wgmma.mma_async.sync.aligned.m64n192k16.f32.bf16.bf16 {%0, %1, %2, %3, %4, %5, %6, %7, %8, %9, %10, %11, %12, %13, %14, %15, %16, %17, %18, %19, %20, %21, %22, %23, %24, %25, %26, %27, %28, %29, %30, %31, %32, %33, %34, %35, %36, %37, %38, %39, %40, %41, %42, %43, %44, %45, %46, %47, %48, %49, %50, %51, %52, %53, %54, %55, %56, %57, %58, %59, %60, %61, %62, %63, %64, %65, %66, %67, %68, %69, %70, %71, %72, %73, %74, %75, %76, %77, %78, %79, %80, %81, %82, %83, %84, %85, %86, %87, %88, %89, %90, %91, %92, %93, %94, %95}, {%96,%97,%98,%99}, db, p, 1, 1, %102;\n}\n"
    : "+f"(d[0]), "+f"(d[1]), "+f"(d[2]), "+f"(d[3]), "+f"(d[4]), "+f"(d[5]), "+f"(d[6]), "+f"(d[7]), "+f"(d[8]), "+f"(d[9]), "+f"(d[10]), "+f"(d[11]), "+f"(d[12]), "+f"(d[13]), "+f"(d[14]), "+f"(d[15]), "+f"(d[16]), "+f"(d[17]), "+f"(d[18]), "+f"(d[19]), "+f"(d[20]), "+f"(d[21]), "+f"(d[22]), "+f"(d[23]), "+f"(d[24]), "+f"(d[25]), "+f"(d[26]), "+f"(d[27]), "+f"(d[28]), "+f"(d[29]), "+f"(d[30]), "+f"(d[31]), "+f"(e[0]), "+f"(e[1]), "+f"(e[2]), "+f"(e[3]), "+f"(e[4]), "+f"(e[5]), "+f"(e[6]), "+f"(e[7]), "+f"(e[8]), "+f"(e[9]), "+f"(e[10]), "+f"(e[11]), "+f"(e[12]), "+f"(e[13]), "+f"(e[14]), "+f"(e[15]), "+f"(e[16]), "+f"(e[17]), "+f"(e[18]), "+f"(e[19]), "+f"(e[20]), "+f"(e[21]), "+f"(e[22]), "+f"(e[23]), "+f"(e[24]), "+f"(e[25]), "+f"(e[26]), "+f"(e[27]), "+f"(e[28]), "+f"(e[29]), "+f"(e[30]), "+f"(e[31]), "+f"(f[0]), "+f"(f[1]), "+f"(f[2]), "+f"(f[3]), "+f"(f[4]), "+f"(f[5]), "+f"(f[6]), "+f"(f[7]), "+f"(f[8]), "+f"(f[9]), "+f"(f[10]), "+f"(f[11]), "+f"(f[12]), "+f"(f[13]), "+f"(f[14]), "+f"(f[15]), "+f"(f[16]), "+f"(f[17]), "+f"(f[18]), "+f"(f[19]), "+f"(f[20]), "+f"(f[21]), "+f"(f[22]), "+f"(f[23]), "+f"(f[24]), "+f"(f[25]), "+f"(f[26]), "+f"(f[27]), "+f"(f[28]), "+f"(f[29]), "+f"(f[30]), "+f"(f[31])
    : "r"(a0), "r"(a1), "r"(a2), "r"(a3), "r"(db), "r"(sc), "n"(TB), "n"(HB));
}
template<int TA, int TB, uint32_t HA, uint32_t HB> __device__ __forceinline__ void wgmma_ss_n128(float (&d)[64], uint32_t da, uint32_t db, int sc) {
  asm volatile("{\n.reg .pred p;\n.reg .b64 da, db;\nsetp.ne.b32 p, %66, 0;\nmov.b64 da, {%64, %69};\nmov.b64 db, {%65, %70};\n"
    "wgmma.mma_async.sync.aligned.m64n128k16.f32.bf16.bf16 {%0, %1, %2, %3, %4, %5, %6, %7, %8, %9, %10, %11, %12, %13, %14, %15, %16, %17, %18, %19, %20, %21, %22, %23, %24, %25, %26, %27, %28, %29, %30, %31, %32, %33, %34, %35, %36, %37, %38, %39, %40, %41, %42, %43, %44, %45, %46, %47, %48, %49, %50, %51, %52, %53, %54, %55, %56, %57, %58, %59, %60, %61, %62, %63}, da, db, p, 1, 1, %67, %68;\n}\n"
    : "+f"(d[0]), "+f"(d[1]), "+f"(d[2]), "+f"(d[3]), "+f"(d[4]), "+f"(d[5]), "+f"(d[6]), "+f"(d[7]), "+f"(d[8]), "+f"(d[9]), "+f"(d[10]), "+f"(d[11]), "+f"(d[12]), "+f"(d[13]), "+f"(d[14]), "+f"(d[15]), "+f"(d[16]), "+f"(d[17]), "+f"(d[18]), "+f"(d[19]), "+f"(d[20]), "+f"(d[21]), "+f"(d[22]), "+f"(d[23]), "+f"(d[24]), "+f"(d[25]), "+f"(d[26]), "+f"(d[27]), "+f"(d[28]), "+f"(d[29]), "+f"(d[30]), "+f"(d[31]), "+f"(d[32]), "+f"(d[33]), "+f"(d[34]), "+f"(d[35]), "+f"(d[36]), "+f"(d[37]), "+f"(d[38]), "+f"(d[39]), "+f"(d[40]), "+f"(d[41]), "+f"(d[42]), "+f"(d[43]), "+f"(d[44]), "+f"(d[45]), "+f"(d[46]), "+f"(d[47]), "+f"(d[48]), "+f"(d[49]), "+f"(d[50]), "+f"(d[51]), "+f"(d[52]), "+f"(d[53]), "+f"(d[54]), "+f"(d[55]), "+f"(d[56]), "+f"(d[57]), "+f"(d[58]), "+f"(d[59]), "+f"(d[60]), "+f"(d[61]), "+f"(d[62]), "+f"(d[63])
    : "r"(da), "r"(db), "r"(sc), "n"(TA), "n"(TB), "n"(HA), "n"(HB));
}
template<int TA, int TB, uint32_t HA, uint32_t HB> __device__ __forceinline__ void wgmma_ss_n96(float (&d)[48], uint32_t da, uint32_t db, int sc) {
  asm volatile("{\n.reg .pred p;\n.reg .b64 da, db;\nsetp.ne.b32 p, %50, 0;\nmov.b64 da, {%48, %53};\nmov.b64 db, {%49, %54};\n"
    "wgmma.mma_async.sync.aligned.m64n96k16.f32.bf16.bf16 {%0, %1, %2, %3, %4, %5, %6, %7, %8, %9, %10, %11, %12, %13, %14, %15, %16, %17, %18, %19, %20, %21, %22, %23, %24, %25, %26, %27, %28, %29, %30, %31, %32, %33, %34, %35, %36, %37, %38, %39, %40, %41, %42, %43, %44, %45, %46, %47}, da, db, p, 1, 1, %51, %52;\n}\n"
    : "+f"(d[0]), "+f"(d[1]), "+f"(d[2]), "+f"(d[3]), "+f"(d[4]), "+f"(d[5]), "+f"(d[6]), "+f"(d[7]), "+f"(d[8]), "+f"(d[9]), "+f"(d[10]), "+f"(d[11]), "+f"(d[12]), "+f"(d[13]), "+f"(d[14]), "+f"(d[15]), "+f"(d[16]), "+f"(d[17]), "+f"(d[18]), "+f"(d[19]), "+f"(d[20]), "+f"(d[21]), "+f"(d[22]), "+f"(d[23]), "+f"(d[24]), "+f"(d[25]), "+f"(d[26]), "+f"(d[27]), "+f"(d[28]), "+f"(d[29]), "+f"(d[30]), "+f"(d[31]), "+f"(d[32]), "+f"(d[33]), "+f"(d[34]), "+f"(d[35]), "+f"(d[36]), "+f"(d[37]), "+f"(d[38]), "+f"(d[39]), "+f"(d[40]), "+f"(d[41]), "+f"(d[42]), "+f"(d[43]), "+f"(d[44]), "+f"(d[45]), "+f"(d[46]), "+f"(d[47])
    : "r"(da), "r"(db), "r"(sc), "n"(TA), "n"(TB), "n"(HA), "n"(HB));
}
template<int TA, int TB, uint32_t HA, uint32_t HB> __device__ __forceinline__ void wgmma_ss3_n192(float (&d)[32], float (&e)[32], float (&f)[32], uint32_t da, uint32_t db, int sc) {
  asm volatile("{\n.reg .pred p;\n.reg .b64 da, db;\nsetp.ne.b32 p, %98, 0;\nmov.b64 da, {%96, %101};\nmov.b64 db, {%97, %102};\n"
    "wgmma.mma_async.sync.aligned.m64n192k16.f32.bf16.bf16 {%0, %1, %2, %3, %4, %5, %6, %7, %8, %9, %10, %11, %12, %13, %14, %15, %16, %17, %18, %19, %20, %21, %22, %23, %24, %25, %26, %27, %28, %29, %30, %31, %32, %33, %34, %35, %36, %37, %38, %39, %40, %41, %42, %43, %44, %45, %46, %47, %48, %49, %50, %51, %52, %53, %54, %55, %56, %57, %58, %59, %60, %61, %62, %63, %64, %65, %66, %67, %68, %69, %70, %71, %72, %73, %74, %75, %76, %77, %78, %79, %80, %81, %82, %83, %84, %85, %86, %87, %88, %89, %90, %91, %92, %93, %94, %95}, da, db, p, 1, 1, %99, %100;\n}\n"
    : "+f"(d[0]), "+f"(d[1]), "+f"(d[2]), "+f"(d[3]), "+f"(d[4]), "+f"(d[5]), "+f"(d[6]), "+f"(d[7]), "+f"(d[8]), "+f"(d[9]), "+f"(d[10]), "+f"(d[11]), "+f"(d[12]), "+f"(d[13]), "+f"(d[14]), "+f"(d[15]), "+f"(d[16]), "+f"(d[17]), "+f"(d[18]), "+f"(d[19]), "+f"(d[20]), "+f"(d[21]), "+f"(d[22]), "+f"(d[23]), "+f"(d[24]), "+f"(d[25]), "+f"(d[26]), "+f"(d[27]), "+f"(d[28]), "+f"(d[29]), "+f"(d[30]), "+f"(d[31]), "+f"(e[0]), "+f"(e[1]), "+f"(e[2]), "+f"(e[3]), "+f"(e[4]), "+f"(e[5]), "+f"(e[6]), "+f"(e[7]), "+f"(e[8]), "+f"(e[9]), "+f"(e[10]), "+f"(e[11]), "+f"(e[12]), "+f"(e[13]), "+f"(e[14]), "+f"(e[15]), "+f"(e[16]), "+f"(e[17]), "+f"(e[18]), "+f"(e[19]), "+f"(e[20]), "+f"(e[21]), "+f"(e[22]), "+f"(e[23]), "+f"(e[24]), "+f"(e[25]), "+f"(e[26]), "+f"(e[27]), "+f"(e[28]), "+f"(e[29]), "+f"(e[30]), "+f"(e[31]), "+f"(f[0]), "+f"(f[1]), "+f"(f[2]), "+f"(f[3]), "+f"(f[4]), "+f"(f[5]), "+f"(f[6]), "+f"(f[7]), "+f"(f[8]), "+f"(f[9]), "+f"(f[10]), "+f"(f[11]), "+f"(f[12]), "+f"(f[13]), "+f"(f[14]), "+f"(f[15]), "+f"(f[16]), "+f"(f[17]), "+f"(f[18]), "+f"(f[19]), "+f"(f[20]), "+f"(f[21]), "+f"(f[22]), "+f"(f[23]), "+f"(f[24]), "+f"(f[25]), "+f"(f[26]), "+f"(f[27]), "+f"(f[28]), "+f"(f[29]), "+f"(f[30]), "+f"(f[31])
    : "r"(da), "r"(db), "r"(sc), "n"(TA), "n"(TB), "n"(HA), "n"(HB));
}

__device__ __forceinline__ void mbar_init(uint32_t b, uint32_t c) { asm volatile("mbarrier.init.shared::cta.b64 [%0], %1;" :: "r"(b), "r"(c) : "memory"); }
__device__ __forceinline__ void mbar_expect(uint32_t b, uint32_t n) { asm volatile("mbarrier.arrive.expect_tx.shared::cta.b64 _, [%0], %1;" :: "r"(b), "r"(n) : "memory"); }
__device__ __forceinline__ void mbar_arrive(uint32_t b) { asm volatile("mbarrier.arrive.shared::cta.b64 _, [%0];" :: "r"(b) : "memory"); }
__device__ __forceinline__ void mbar_wait(uint32_t b, uint32_t ph) {
  asm volatile("{\n.reg .pred p;\nW_LOOP:\n.pragma \"nounroll\";\nmbarrier.try_wait.parity.shared::cta.b64 p, [%0], %1;\n@!p bra.uni W_LOOP;\n}" :: "r"(b), "r"(ph) : "memory");
}
__device__ __forceinline__ void watchdog_wait(uint32_t b, long long t0) {
  uint32_t ok;
#pragma unroll 1
  do {
    asm volatile("{\n.reg .pred p;\nmbarrier.try_wait.parity.shared::cta.b64 p, [%1], 0;\nselp.u32 %0, 1, 0, p;\n}" : "=r"(ok) : "r"(b) : "memory");
    if (!ok && clock64() - t0 > WATCHDOG_CLKS) { asm volatile("st.global.b32 [%0], %1;" :: "l"(0ull), "r"(0) : "memory"); ok = 1; }
  } while (!ok);
}
__device__ __forceinline__ void warp_arrive(uint32_t b) {
  asm volatile("{\n.reg .pred p;\nelect.sync _|p, 0xffffffff;\n@p mbarrier.arrive.shared::cta.b64 _, [%0];\n}" :: "r"(b) : "memory");
}
__device__ __forceinline__ void cut() { asm volatile("pmevent.mask 0;" ::: "memory"); }
__device__ __forceinline__ void pin(float& a) { asm volatile("" : "+f"(a) :: "memory"); }
__device__ __forceinline__ void pin(uint32_t& a) { asm volatile("" : "+r"(a) :: "memory"); }
__device__ __forceinline__ bool elect_one() {
  uint32_t e;
  asm volatile("{\n.reg .pred p;\nelect.sync _|p, 0xffffffff;\nselp.u32 %0, 1, 0, p;\n}" : "=r"(e));
  return e;
}
__device__ __forceinline__ void bulk1(uint32_t dst, const void* src, uint32_t n, uint32_t bar) {
  asm volatile("cp.async.bulk.shared::cluster.global.mbarrier::complete_tx::bytes [%0], [%1], %2, [%3];"
               :: "r"(dst), "l"(src), "r"(n), "r"(bar) : "memory");
}
__device__ __forceinline__ void tma2(uint32_t dst, const CUtensorMap* m, uint32_t bar, int c0, int c1) {
  asm volatile("cp.async.bulk.tensor.2d.shared::cluster.global.mbarrier::complete_tx::bytes [%0], [%1, {%3, %4}], [%2];"
               :: "r"(dst), "l"(m), "r"(bar), "r"(c0), "r"(c1) : "memory");
}
__device__ __forceinline__ void tma3(uint32_t dst, const CUtensorMap* m, uint32_t bar, int c0, int c1, int c2) {
  asm volatile("cp.async.bulk.tensor.3d.shared::cluster.global.mbarrier::complete_tx::bytes [%0], [%1, {%3, %4, %5}], [%2];"
               :: "r"(dst), "l"(m), "r"(bar), "r"(c0), "r"(c1), "r"(c2) : "memory");
}
__device__ __forceinline__ void tma4(uint32_t dst, const CUtensorMap* m, uint32_t bar, int c0, int c1, int c2, int c3) {
  asm volatile("cp.async.bulk.tensor.4d.shared::cluster.global.mbarrier::complete_tx::bytes [%0], [%1, {%3, %4, %5, %6}], [%2];"
               :: "r"(dst), "l"(m), "r"(bar), "r"(c0), "r"(c1), "r"(c2), "r"(c3) : "memory");
}
__device__ __forceinline__ void tma5(uint32_t dst, const CUtensorMap* m, uint32_t bar, int c0, int c1, int c2, int c3, int c4) {
  asm volatile("cp.async.bulk.tensor.5d.shared::cluster.global.mbarrier::complete_tx::bytes [%0], [%1, {%3, %4, %5, %6, %7}], [%2];"
               :: "r"(dst), "l"(m), "r"(bar), "r"(c0), "r"(c1), "r"(c2), "r"(c3), "r"(c4) : "memory");
}
__device__ __forceinline__ void cluster_arrive() { asm volatile("barrier.cluster.arrive.relaxed.aligned;" ::: "memory"); }
__device__ __forceinline__ void cluster_wait() { asm volatile("barrier.cluster.wait.aligned;" ::: "memory"); }
__device__ __forceinline__ uint32_t mapa(uint32_t a, uint32_t cta) { uint32_t r; asm("mapa.shared::cluster.u32 %0, %1, %2;" : "=r"(r) : "r"(a), "r"(cta)); return r; }
__device__ __forceinline__ void prefetch_map(const CUtensorMap* m) { asm volatile("prefetch.tensormap [%0];" :: "l"(m) : "memory"); }
constexpr uint32_t H128 = (1024 >> 4) | (1u << 30), H64 = (512 >> 4) | (2u << 30);
__device__ constexpr uint32_t dlo(uint32_t off, uint32_t lbo) { return (off >> 4) + ((lbo >> 4) << 16); }
__device__ __forceinline__ void wg_fence()  { asm volatile("wgmma.fence.sync.aligned;" ::: "memory"); }
__device__ __forceinline__ void wg_commit() { asm volatile("wgmma.commit_group.sync.aligned;" ::: "memory"); }
template <int N> __device__ __forceinline__ void wg_wait() { asm volatile("wgmma.wait_group.sync.aligned %0;" :: "n"(N) : "memory"); }
template <int N> __device__ __forceinline__ void reg_fence(float (&a)[N]) {
#pragma unroll
  for (int i = 0; i < N; i++) asm volatile("" : "+f"(a[i]) :: "memory");
}
__device__ __forceinline__ uint32_t pack2(float lo, float hi) {
  uint32_t r; asm("cvt.rn.bf16x2.f32 %0, %1, %2;" : "=r"(r) : "f"(hi), "f"(lo)); return r;
}
__device__ __forceinline__ uint32_t mul2(uint32_t a, uint32_t b) { uint32_t r; asm("mul.rn.bf16x2 %0, %1, %2;" : "=r"(r) : "r"(a), "r"(b)); return r; }
__device__ __forceinline__ uint32_t add2(uint32_t a, uint32_t b) { uint32_t r; asm("add.rn.bf16x2 %0, %1, %2;" : "=r"(r) : "r"(a), "r"(b)); return r; }
__device__ __forceinline__ float bf_lo(uint32_t v) { return __uint_as_float(v << 16); }
__device__ __forceinline__ float bf_hi(uint32_t v) { return __uint_as_float(v & 0xffff0000u); }
__device__ __forceinline__ float bf_round(float v) { return __bfloat162float(__float2bfloat16_rn(v)); }
__device__ __forceinline__ float2 lds64f(uint32_t a) {
  float2 v; asm volatile("ld.shared.v2.f32 {%0,%1}, [%2];" : "=f"(v.x), "=f"(v.y) : "r"(a) : "memory"); return v;
}
__device__ __forceinline__ uint4 lds128(uint32_t a) {
  uint4 v; asm volatile("ld.shared.v4.b32 {%0,%1,%2,%3}, [%4];" : "=r"(v.x), "=r"(v.y), "=r"(v.z), "=r"(v.w) : "r"(a) : "memory"); return v;
}
__device__ __forceinline__ uint4 ld_pkt(const uint4* p) {
  uint4 v;
  asm volatile("ld.relaxed.gpu.global.v4.b32 {%0, %1, %2, %3}, [%4];" : "=r"(v.x), "=r"(v.y), "=r"(v.z), "=r"(v.w) : "l"(p) : "memory");
  return v;
}
__device__ __forceinline__ void st_pkt2(uint2* p, float a, float b, uint32_t tag) {
  asm volatile("{\n.reg .b32 t;\nlop3.b32 t, %1, %3, 1, 0xD8;\nst.relaxed.gpu.global.v2.b32 [%0], {t, %2};\n}"
               :: "l"(p), "r"(__float_as_uint(a)), "r"(__float_as_uint(b)), "r"(tag) : "memory");
}
__device__ __forceinline__ uint2 ld_pkt2(const uint2* p) {
  uint2 v; asm volatile("ld.relaxed.gpu.global.v2.b32 {%0, %1}, [%2];" : "=r"(v.x), "=r"(v.y) : "l"(p) : "memory"); return v;
}
template <class T> __device__ __forceinline__ T* opaque(T* p) { return (T*)__shfl_sync(~0u, (unsigned long long)p, threadIdx.x & 31); }
__device__ __forceinline__ uint32_t opaque32(uint32_t v) { return __shfl_sync(~0u, v, threadIdx.x & 31); }
__device__ __forceinline__ float ex2(float x) { float y; asm("ex2.approx.ftz.f32 %0, %1;" : "=f"(y) : "f"(x)); return y; }
__device__ __forceinline__ float rcp(float x) { float y; asm("rcp.approx.ftz.f32 %0, %1;" : "=f"(y) : "f"(x)); return y; }
#define CMUL(or_, oi_, ar, ai, br, bi) do { float t_r = (ar) * (br) - (ai) * (bi); float t_i = (ar) * (bi) + (ai) * (br); or_ = t_r; oi_ = t_i; } while (0)

struct Mish {
  float t[3][2], e[2], r[2], s[2], n[2];
  float2 bc, bn;
  uint32_t baddr;
};
template <int P>
__device__ __forceinline__ void mish_step(Mish& m, float (&A)[64], float (&Bc)[48], uint32_t (&fa)[32], uint32_t (&fb)[24]) {
  if constexpr (P >= 2 && P < 58) {
    constexpr int Q = P - 2;
    uint32_t o = pack2(m.t[Q % 3][0] * fmaf(m.r[0], m.n[Q & 1], m.s[Q & 1]), m.t[Q % 3][1] * fmaf(m.r[1], m.n[Q & 1], m.s[Q & 1]));
    pin(o);
    if constexpr (Q < 32) fa[Q] = o; else fb[Q - 32] = o;
  }
  if constexpr (P >= 1 && P < 57) {
    const float e0 = m.e[0] + 1.f, e1 = m.e[1] + 1.f;
    m.r[0] = rcp(fmaf(e0, e0, 1.f)); m.r[1] = rcp(fmaf(e1, e1, 1.f));
    pin(m.r[0]); pin(m.r[1]);
  }
  if constexpr (P < 56) {
    if constexpr ((P & 1) == 0) { m.bc = m.bn; m.bn = lds64f(m.baddr + 32 * (P / 2 + 1)); }
    float a0, a1;
    if constexpr (P < 32) { a0 = A[2 * P]; a1 = A[2 * P + 1]; } else { a0 = Bc[2 * P - 64]; a1 = Bc[2 * P - 63]; }
    pin(a0); pin(a1);
    m.t[P % 3][0] = fmaf(a0, 1.4426950408889634f, m.bc.x); m.t[P % 3][1] = fmaf(a1, 1.4426950408889634f, m.bc.y);
    m.e[0] = ex2(m.t[P % 3][0]); m.e[1] = ex2(m.t[P % 3][1]);
    pin(m.e[0]); pin(m.e[1]);
  }
}
template <class... T> __device__ constexpr int mish_pos(int i, T... d) {
  const int a[] = {d...};
  int p = 0;
  for (int k = 0; k < i; k++) p += a[k];
  return p;
}
template <int P0, int P1>
__device__ __forceinline__ void mish_run(Mish& m, float (&A)[64], float (&Bc)[48], uint32_t (&fa)[32], uint32_t (&fb)[24]) {
  if constexpr (P0 < P1) { mish_step<P0>(m, A, Bc, fa, fb); mish_run<P0 + 1, P1>(m, A, Bc, fa, fb); }
}

__device__ __forceinline__ void pack_piece(uint32_t (&pk)[16], float (&acc)[32]) {
#pragma unroll
  for (int i = 0; i < 16; i++) { pin(acc[2 * i]); pin(acc[2 * i + 1]); pk[i] = pack2(acc[2 * i], acc[2 * i + 1]); pin(pk[i]); }
}
template <int I>
__device__ __forceinline__ void give_pkt(const uint32_t (&pk)[16], uint32_t dst, uint32_t bar) {
  asm volatile("st.async.shared::cluster.mbarrier::complete_tx::bytes.v4.b32 [%0], {%1,%2,%3,%4}, [%5];"
               :: "r"(dst + I * 512), "r"(pk[4 * I]), "r"(pk[4 * I + 1]), "r"(pk[4 * I + 2]), "r"(pk[4 * I + 3]), "r"(bar) : "memory");
}
__device__ __forceinline__ void stage_piece(float (&acc)[32], uint32_t dst) {
#pragma unroll
  for (int i = 0; i < 4; i++) {
#pragma unroll
    for (int j = 0; j < 8; j++) pin(acc[8 * i + j]);
    asm volatile("st.shared.v4.b32 [%0], {%1,%2,%3,%4};" :: "r"(dst + i * 512), "r"(pack2(acc[8 * i], acc[8 * i + 1])), "r"(pack2(acc[8 * i + 2], acc[8 * i + 3])),
                 "r"(pack2(acc[8 * i + 4], acc[8 * i + 5])), "r"(pack2(acc[8 * i + 6], acc[8 * i + 7])) : "memory");
  }
}
__device__ __forceinline__ void take_piece(uint4 (&in)[4], uint32_t src) {
#pragma unroll
  for (int i = 0; i < 4; i++) in[i] = lds128(src + i * 512);
}
__device__ __forceinline__ void stage_sum(float (&acc)[32], uint4 (&nb)[4], uint32_t dst, uint32_t tag) {
#pragma unroll
  for (int i = 0; i < 4; i++) {
    uint32_t w0;
#pragma unroll
    for (int j = 0; j < 8; j++) pin(acc[8 * i + j]);
    asm("lop3.b32 %0, %1, %2, 1, 0xD8;" : "=r"(w0) : "r"(add2(pack2(acc[8 * i], acc[8 * i + 1]), nb[i].x)), "r"(tag));
    asm volatile("st.shared.v4.b32 [%0], {%1,%2,%3,%4};" :: "r"(dst + i * 512), "r"(w0), "r"(add2(pack2(acc[8 * i + 2], acc[8 * i + 3]), nb[i].y)),
                 "r"(add2(pack2(acc[8 * i + 4], acc[8 * i + 5]), nb[i].z)), "r"(add2(pack2(acc[8 * i + 6], acc[8 * i + 7]), nb[i].w)) : "memory");
  }
}
__device__ __forceinline__ void recv_issue(uint4 (&in)[4], const uint4* src) {
#pragma unroll
  for (int i = 0; i < 4; i++) in[i] = ld_pkt(src + i * 32);
}
__device__ __forceinline__ void recv_check(uint4 (&in)[4], const uint4* src, uint32_t tag) {
  if (__builtin_expect(__any_sync(~0u, ((in[0].x ^ tag) | (in[1].x ^ tag) | (in[2].x ^ tag) | (in[3].x ^ tag)) & 1u), 0)) {
    int it = 0;
#pragma unroll 1
    do { recv_issue(in, src); }
    while (__any_sync(~0u, ((in[0].x ^ tag) | (in[1].x ^ tag) | (in[2].x ^ tag) | (in[3].x ^ tag)) & 1u) && ++it < SPIN_LIMIT);
  }
#pragma unroll
  for (int i = 0; i < 4; i++) in[i].x &= ~1u;
}
template <bool SET>
__device__ __forceinline__ void recv_add(float (&sum)[32], uint4 (&in)[4], float g0, float g1) {
#pragma unroll
  for (int i = 0; i < 4; i++) {
    pin(in[i].x); pin(in[i].y); pin(in[i].z); pin(in[i].w);
    const float v[8] = {bf_lo(in[i].x), bf_hi(in[i].x), bf_lo(in[i].y), bf_hi(in[i].y), bf_lo(in[i].z), bf_hi(in[i].z), bf_lo(in[i].w), bf_hi(in[i].w)};
#pragma unroll
    for (int j = 0; j < 8; j++) {
      sum[8 * i + j] = SET ? ((j & 2) ? g1 : g0) * v[j] : fmaf((j & 2) ? g1 : g0, v[j], sum[8 * i + j]);
      pin(sum[8 * i + j]);
    }
  }
}

template <bool BASE1K>
__global__ void __cluster_dims__(2, 1, 1) __launch_bounds__(384, 1) fused_kernel(const __grid_constant__ Params p, const __grid_constant__ Maps tm) {
  extern __shared__ __align__(1024) unsigned char smem[];
  const uint32_t sb = (uint32_t)__cvta_generic_to_shared(smem);
  const uint32_t bars = sb + BAR_OFF;
  const uint32_t sbc = sb;
  const int tid = threadIdx.x;
  const int warp = __shfl_sync(~0u, tid >> 5, 0);
  const int bid = blockIdx.x;
  const int cl = bid >> 1, c7 = ((cl - 36) * 37) >> 8;
  const int m = cl < 4 ? 15 : cl < 36 ? (cl - 4) & 7 : cl - 28 - 7 * c7;
  const int f = (bid & 1) | ((cl < 4 ? cl : cl < 36 ? (cl - 4) >> 3 : c7) << 1);
  const int o = f & 1, rot = f & 6;
  const int colA = 224 * f + ((f & 1) ? 96 : 0), colB = 224 * f + ((f & 1) ? 0 : 128);

  const __nv_bfloat16* pf = (&p.xp)[tid < 16 ? 0 : tid < 20 ? 1 : 2];
  pf += (tid < 16 ? 128 * m + 16 * f + tid : 64 * f + 4 * m + (tid & 3)) * DM;
  asm volatile("{\n.reg .pred p;\nsetp.lt.s32 p, %1, 24;\n@p prefetch.global.L2 [%0];\n}" :: "l"(pf), "r"(tid) : "memory");
  if (warp == 8) {
    if (elect_one()) {
      mbar_init(bars + XFULL, 1); mbar_init(bars + FULL, 1);
      mbar_expect(bars + XFULL, 16384);
      tma5(sb + X_OFF + ((0 - rot) & 7) * 16384, &tm.x, bars + XFULL, 0, 0, 0, 0, m);
      mbar_expect(bars + FULL, 16384);
      tma4(sb + RING_OFF, &tm.b, bars + FULL, 0, 0, 0, 8 * f);
#pragma unroll
      for (int kb = 1; kb < 8; kb++) { mbar_init(bars + XFULL + 8 * kb, 1); if (kb < NSLOT) mbar_init(bars + FULL + 8 * kb, 1); }
      asm volatile("fence.mbarrier_init.release.cluster;" ::: "memory");
    }
    __syncwarp();
  } else if (warp == 9) {
    if (elect_one()) {
#pragma unroll 1
      for (int i = 0; i < 8; i++) { mbar_init(bars + EMPTY + 8 * i, 8); mbar_init(bars + DBAR + 8 * i, 1); mbar_expect(bars + DBAR + 8 * i, 8192); }
      mbar_init(bars + GBAR, 3); mbar_init(bars + RDY, 8); mbar_init(bars + ZBAR, 8); mbar_init(bars + LBAR, 2); mbar_init(bars + HRDY, 1); mbar_init(bars + DONE, 8);
      asm volatile("fence.mbarrier_init.release.cluster;" ::: "memory");
    }
    __syncwarp();
  } else if (warp == 10) {
    if (elect_one()) {
#pragma unroll 1
      for (int i = 0; i < 10; i++) mbar_init(bars + XBAR + 8 * i, 4);
      asm volatile("fence.mbarrier_init.release.cluster;" ::: "memory");
    }
    __syncwarp();
  }
  cluster_arrive();
  asm volatile("{\n.reg .pred p;\nsetp.lt.s32 p, %1, 24;\n@p prefetch.global.L2 [%0 + 128];\n}" :: "l"(pf), "r"(tid) : "memory");

  if (warp >= 8) {
    asm volatile("setmaxnreg.dec.sync.aligned.u32 40;");
    const int l = tid & 31;
    if (warp == 8) {
      const bool lead = elect_one();
      if (lead) {
#pragma unroll 1
        for (int kb = 1; kb < 8; kb++) {
          const uint32_t xb = bars + XFULL + 8 * kb, fb = bars + FULL + 8 * kb;
          mbar_expect(xb, kb == 7 ? 16384 + 128 : 16384);
          tma5(sb + X_OFF + ((kb - rot) & 7) * 16384, &tm.x, xb, kb * 64, 0, 0, 0, m);
          if (kb < NSLOT) {
            mbar_expect(fb, 16384);
            tma4(sb + RING_OFF + kb * 16384, &tm.b, fb, kb * 64, 0, 0, 8 * f);
          }
        }
      }
      __syncwarp();
      cluster_wait();
      if (lead) {
        bulk1(sb + DSK_OFF, p.dskip + 64 * f, 128, bars + XFULL + 8 * 7);
        prefetch_map(&tm.w1a); prefetch_map(&tm.w1b); prefetch_map(&tm.w2a); prefetch_map(&tm.w2b); prefetch_map(&tm.cre); prefetch_map(&tm.cim); prefetch_map(&tm.y);
        int s = 0;
        uint32_t par = 0;
#pragma unroll 1
        for (int i = NSLOT; i < 24; i++) {
          const uint32_t fb = bars + FULL + 8 * s, dst = sb + RING_OFF + s * 16384;
          mbar_wait(bars + EMPTY + 8 * s, par);
          if (i < 8) { mbar_expect(fb, 16384); tma4(dst, &tm.b, fb, i * 64, 0, 0, 8 * f); }
          else {
            const bool a = i < 16;
            mbar_expect(fb, a ? 16384 : 12288);
            tma3(dst, a ? &tm.w1a : &tm.w1b, fb, 0, (((a ? i : i ^ 2) + rot) & 7) * 64, a ? colA >> 6 : colB >> 5);
          }
          if (++s == NSLOT) { s = 0; par ^= 1; }
        }
#pragma unroll 1
        for (int j = 0; j < 6; j++) {
          const uint32_t fb = bars + FULL + 8 * j, dst = sb + RING_OFF + (j & 3) * 24576;
          const int half = j >= 4 ? 48 : 64, row = (j >= 4 ? colB : colA) + (j & 1) * half;
          const CUtensorMap* mp = j == 0 ? &tm.cre : j == 1 ? &tm.cim : j < 4 ? &tm.w2a : &tm.w2b;
          mbar_wait(bars + EMPTY + 8 * ((0x105421 >> (4 * j)) & 7), j < 4);
          mbar_expect(fb, half * 384);
#pragma unroll
          for (int t = 0; t < 3; t++) {
            const int pc = (f ^ (7 - 2 * t)) * 64;
            tma2(dst + t * half * 128, mp, fb, j < 2 ? f * 64 : pc, j < 2 ? pc : row);
          }
        }
        s = 0; par = 1;
#pragma unroll 1
        for (int i = 0; i < 15; i++) {
          const int kind = i < 6 ? (0x212010 >> (4 * i)) & 3 : (s >= 3 ? s - 3 : s);
          const int pc = (f ^ ((0x01246 >> (4 * (i < 6 ? (0x34 >> i) & 1 : i / 3))) & 7)) * 64;
          const uint32_t fb = bars + FULL + 8 * s, dst = sb + RING_OFF + (s >= 3 ? s - 3 : s + 3) * 16384;
          mbar_wait(bars + EMPTY + 8 * (i < 6 ? (0x554332 >> (4 * i)) & 7 : s), par ^ 1);
          const int half = kind == 1 ? 48 : 64, row = kind == 0 ? colA : colB;
          mbar_expect(fb, half * 256);
          if (kind == 2) { tma2(dst, &tm.cre, fb, f * 64, pc); tma2(dst + 8192, &tm.cim, fb, f * 64, pc); }
          else {
            const CUtensorMap* mp = kind == 0 ? &tm.w2a : &tm.w2b;
            tma2(dst, mp, fb, pc, row); tma2(dst + half * 128, mp, fb, pc, row + half);
          }
          if (++s == NSLOT) { s = 0; par ^= 1; }
        }
      }
    } else if (warp == 9) {
      float v[7];
#pragma unroll
      for (int i = 0; i < 7; i++) v[i] = __bfloat162float(p.b1[(i < 4 ? colA + 32 * i : colB + 32 * (i - 4)) + l]);
#pragma unroll
      for (int i = 0; i < 7; i++) *(float*)(smem + BIAS_OFF + (32 * i + l) * 4) = v[i] * 1.4426950408889634f;
      cluster_wait();
      __syncwarp();
      if (l == 0) {
        mbar_arrive(bars + GBAR);
        const long long t0 = clock64();
        watchdog_wait(bars + HBAR, t0);
        asm volatile("fence.proxy.async.shared::cta;" ::: "memory");
        mbar_arrive(bars + HRDY);
        watchdog_wait(bars + DONE, t0); watchdog_wait(bars + DBAR + 48, t0); watchdog_wait(bars + DBAR + 56, t0);
      }
    } else {
      const unsigned tag = g_epoch[bid] + 1;
      const int idx = tid - 320;
      uint2* const zp = g_z + m * 64;
      uint4 ga = __ldg((const uint4*)p.gate + l), gb = __ldg((const uint4*)p.gate + 32 + l);
      {
        const float are = __bfloat162float(p.lam_re[64 * f + idx]), aim = __bfloat162float(p.lam_im[64 * f + idx]);
        const float dt = bf_round(expf(__bfloat162float(p.log_dt[64 * f + idx])));
        const float mag = expf(dt * are);
        float sn, cs;
        sincospif((dt * aim) * 0.3183098861837907f, &sn, &cs);
        const float lr = mag * cs, li = mag * sn;
        const float den = 2.f * rcp(are * are + aim * aim), nr = lr - 1.f;
        *(float4*)(smem + GROW_OFF + idx * 16) = make_float4(lr, li, (nr * are + li * aim) * den, (li * are - nr * aim) * den);
      }
      if (idx == 0) *(unsigned*)(smem + BAR_OFF + EPOCH) = tag;
      cluster_wait();
      __syncwarp();
      warp_arrive(bars + LBAR);
      {
        const uint32_t xa = sb + X_OFF + (16 * f + (idx >> 3)) * 128 + (((idx ^ (idx >> 3)) & 7) << 4);
        float a0 = 0.f, a1 = 0.f, b0 = 0.f, b1 = 0.f;
#pragma unroll 1
        for (int kb = 0; kb < 8; kb++) {
          if (kb == 4) ga = gb;
          const int src = 8 * (kb & 3) + (l & 7);
          const uint4 gt = make_uint4(__shfl_sync(~0u, ga.x, src), __shfl_sync(~0u, ga.y, src), __shfl_sync(~0u, ga.z, src), __shfl_sync(~0u, ga.w, src));
          mbar_wait(bars + XFULL + 8 * kb, 0);
          const uint4 u = lds128(xa + ((kb - rot) & 7) * 16384), w = lds128(xa + ((kb - rot) & 7) * 16384 + 1024);
          const uint32_t pu[4] = {mul2(u.x, gt.x), mul2(u.y, gt.y), mul2(u.z, gt.z), mul2(u.w, gt.w)};
          const uint32_t pw[4] = {mul2(w.x, gt.x), mul2(w.y, gt.y), mul2(w.z, gt.z), mul2(w.w, gt.w)};
#pragma unroll
          for (int j = 0; j < 4; j++) { a0 += bf_lo(pu[j]); a1 += bf_hi(pu[j]); b0 += bf_lo(pw[j]); b1 += bf_hi(pw[j]); }
        }
        a0 += a1; b0 += b1;
#pragma unroll
        for (int d = 1; d < 8; d *= 2) { a0 += __shfl_xor_sync(~0u, a0, d); b0 += __shfl_xor_sync(~0u, b0, d); }
        if ((idx & 7) == 0) st_pkt2(zp + 8 * f + (idx >> 3), a0, b0, tag);
      }
      mbar_wait(bars + ZBAR, 0);
      uint2 zz;
      int it = 0;
#pragma unroll 1
      do { zz = ld_pkt2(zp + idx); } while (((zz.x ^ tag) & 1) && ++it < SPIN_LIMIT);
      const float z0 = __uint_as_float(zz.x & ~1u), z1 = __uint_as_float(zz.y);
      const float g0 = bf_round(rcp(1.f + __expf(-bf_round(z0)))), g1 = bf_round(rcp(1.f + __expf(-bf_round(z1))));
      const float c0 = fmaxf(g0, 0x1p-80f), c1 = fmaxf(g1, 0x1p-80f);
      *(float4*)(smem + GROW_OFF + idx * 16) =
          make_float4(c0, c1, bf_round(1.f - g0) * rcp(c0) * 0.6931471805599453f, bf_round(1.f - g1) * rcp(c1) * 0.6931471805599453f);
      __syncwarp();
      if (l == 0) mbar_arrive(bars + GBAR);
      if (elect_one()) {
        const uint32_t w = warp - 10, rsb = mapa(sb, o ^ 1);
#pragma unroll 1
        for (int e = 0; e < 5; e++) {
          mbar_wait(bars + XBAR + 16 * e + 8 * w, 0);
          asm volatile("fence.proxy.async.shared::cta;" ::: "memory");
          if (e < 2) {
            asm volatile("cp.async.bulk.shared::cluster.shared::cta.mbarrier::complete_tx::bytes [%0], [%1], 8192, [%2];"
                         :: "r"(rsb + XB_OFF + (e + 1) * 16384 + w * 8192), "r"(sb + (e ? XB_OFF + 49152 : X_OFF + (o ^ 1) * 16384) + w * 8192),
                            "r"(rsb + BAR_OFF + DBAR + 8 * w + 16 * (e + 1)) : "memory");
          } else {
            const int u = e - 2;
            asm volatile("cp.async.bulk.global.shared::cta.bulk_group [%0], [%1], 8192;"
                         :: "l"(g_part + ((m * NFC + (f ^ (6 - 2 * u))) * 3 + u) * 1024 + w * 512), "r"(sb + XB_OFF + u * 16384 + w * 8192) : "memory");
          }
        }
        asm volatile("cp.async.bulk.commit_group;\ncp.async.bulk.wait_group.read 0;" ::: "memory");
      }
    }
  } else {
    const uint32_t sb = __shfl_sync(~0u, sbc, 0), bars = sb + BAR_OFF;
    const int wg = warp >> 2, v = warp & 3, l = tid & 31, r = l >> 2, q = l & 3;
    const int ch = 32 * wg + 8 * v + r;
    asm volatile("setmaxnreg.inc.sync.aligned.u32 232;");
    const uint32_t db = BASE1K ? 1024 >> 4 : (sb & 0x3FFFF) >> 4;
    const uint32_t dw = db + wg * (8192 >> 4);
    uint2* const agq = opaque(g_agg + f * 64 + ch + (m - 1 - q) * (NFC * 64));
    const uint4* const rbase = opaque(g_part + (m * NFC + f) * (3 * 1024) + warp * 128 + l);
    const uint32_t rsb = mapa(sbc, o ^ 1);
    const uint32_t xbl = opaque32(sb + XB_OFF + warp * 2048 + l * 16), xbr = opaque32(rsb + XB_OFF + warp * 2048 + l * 16);
    const uint32_t dbr = opaque32(rsb + BAR_OFF + DBAR + 8 * wg);
    cluster_wait();
#define RELEASE(s) warp_arrive(bars + EMPTY + 8 * (s))

    float S[64];
    uint32_t y[16], dsk[8];
    float lr, li, lc, m00, m01, m10, m11, l32r, l32i, l64r, l64i, l512r, l512i, w32r, w32i, w128r, w128i, cr, ci;
#define SETUP() do { \
      lr = __uint_as_float(lam.x); lc = __uint_as_float(lam.y); cr = __uint_as_float(lam.z); ci = __uint_as_float(lam.w); \
      m00 = p.swapB ? -ci : cr;  m01 = p.swapB ? cr : -ci; m10 = p.swapB ? -cr : -ci; m11 = p.swapB ? -ci : -cr; \
      li = p.swapB ? -lc : lc; l32r = lr; l32i = li; \
      _Pragma("unroll") for (int i = 0; i < 5; i++) CMUL(l32r, l32i, l32r, l32i, l32r, l32i); \
      CMUL(l64r, l64i, l32r, l32i, l32r, l32i); \
      pin(m00); pin(m01); pin(m10); pin(m11); pin(l64r); pin(l64i); } while (0)
#define POWERS() do { pin(l64r); pin(l64i); \
      float l128r; float l128i; float l256r; float l256i; \
      CMUL(l128r, l128i, l64r, l64i, l64r, l64i); CMUL(l256r, l256i, l128r, l128i, l128r, l128i); CMUL(l512r, l512i, l256r, l256i, l256r, l256i); \
      w32r = (q & 1) ? l32r : 1.f; w32i = (q & 1) ? l32i : 0.f; w128r = (q & 1) ? l128r : 1.f; w128i = (q & 1) ? l128i : 0.f; \
      if (q & 2) { CMUL(w32r, w32i, w32r, w32i, l64r, l64i); CMUL(w128r, w128i, w128r, w128i, l256r, l256i); } \
      pin(l512r); pin(l512i); pin(w32r); pin(w32i); pin(w128r); pin(w128i); } while (0)
#define S_BURST(kb, s) do { wg_fence(); _Pragma("unroll") for (int k = 0; k < 4; k++) \
        wgmma_ss_n128<0, 0, H128, H128>(S, dw + (s) * 1024 + dlo(RING_OFF + k * 32, 16), db + (((kb) - rot) & 7) * 1024 + dlo(X_OFF + k * 32, 16), ((kb) | k) != 0); \
      wg_commit(); } while (0)
#define LOAD_Y(OFF) do { \
      const uint32_t xsk = sb + X_OFF + o * 16384 + (16 * warp + (l & 15)) * 128 + (((l >> 4) ^ (l & 7)) << 4); \
      const uint32_t dsa = sb + (OFF) + 4 * q; \
      _Pragma("unroll") for (int jj = 0; jj < 4; jj++) { \
        asm volatile("ldmatrix.sync.aligned.m8n8.x4.shared.b16 {%0,%1,%2,%3}, [%4];" \
                     : "=r"(y[4 * jj]), "=r"(y[4 * jj + 1]), "=r"(y[4 * jj + 2]), "=r"(y[4 * jj + 3]) : "r"(xsk ^ (jj << 5)) : "memory"); \
        asm volatile("ld.shared.b32 %0, [%1];" : "=r"(dsk[2 * jj]) : "r"(dsa + 32 * jj) : "memory"); \
        asm volatile("ld.shared.b32 %0, [%1];" : "=r"(dsk[2 * jj + 1]) : "r"(dsa + 32 * jj + 16) : "memory"); } } while (0)
#define MUL_Y() do { _Pragma("unroll") for (int j = 0; j < 16; j++) { pin(y[j]); y[j] = mul2(y[j], dsk[j >> 1]); pin(y[j]); } } while (0)
#pragma unroll 1
    for (int kb = 0; kb < 6; kb++) {
      mbar_wait(bars + XFULL + 8 * kb, 0);
      mbar_wait(bars + FULL + 8 * kb, 0);
      S_BURST(kb, kb);
      wg_wait<1>();
      if (kb > 0) RELEASE(kb - 1);
    }
    mbar_wait(bars + LBAR, 0);
    const uint4 lam = lds128(sb + GROW_OFF + ch * 16);
    unsigned epoch;
    asm volatile("ld.shared.b32 %0, [%1];" : "=r"(epoch) : "r"(bars + EPOCH) : "memory");
    mbar_wait(bars + XFULL + 8 * 6, 0); mbar_wait(bars + FULL, 1);
    S_BURST(6, 0); wg_wait<1>(); RELEASE(5); cut();
    SETUP(); cut();
    mbar_wait(bars + XFULL + 8 * 7, 0); mbar_wait(bars + FULL + 8, 1);
    S_BURST(7, 1); wg_wait<1>(); RELEASE(0); cut();
    POWERS(); cut();

#define KBLOCK(I, MMA, SIDE0, SIDE1) do { \
      mbar_wait(bars + FULL + 8 * ((I) % NSLOT), ((I) / NSLOT) & 1); \
      wg_fence(); MMA(0); MMA(1); wg_commit(); cut(); SIDE0; cut(); \
      wg_fence(); MMA(2); MMA(3); wg_commit(); wg_wait<2>(); RELEASE(((I) - 1) % NSLOT); cut(); SIDE1; cut(); } while (0)

    float A[64];
    uint32_t hp[32];
    float hr = 0.f, hi = 0.f, er, ei, g0, g1;
    Mish ms;
    uint2 ag[4];
#define MMA_A(kb, k) wgmma_ss_n128<0, 1, H128, H128>(A, dw + dlo(X_OFF + (kb) * 16384 + (k) * 32, 16), db + dlo(RING_OFF + ((8 + (kb)) % NSLOT) * 16384 + (k) * 2048, 8192), ((kb) | (k)) != 0)
#define SCAN1(T0, T1) do { pin(hr); pin(hi); \
      _Pragma("unroll") for (int t = (T0); t < (T1); t++) { \
        const int ia = 4 * (t >> 1) + (t & 1), ib = ia + 2; \
        const float tr = fmaf(-li, hi, S[ia]), ti = fmaf(li, hr, S[ib]); \
        hr = fmaf(lr, hr, tr); hi = fmaf(lr, hi, ti); } \
      pin(hr); pin(hi); } while (0)
#define PREMUL(T0, T1) do { \
      _Pragma("unroll") for (int t = (T0); t < (T1); t++) { \
        const int ia = 4 * (t >> 1) + (t & 1), ib = ia + 2; \
        pin(S[ia]); pin(S[ib]); \
        const float ur = fmaf(m00, S[ia], m01 * S[ib]), ui = fmaf(m10, S[ia], m11 * S[ib]); \
        S[ia] = ur; S[ib] = ui; pin(S[ia]); pin(S[ib]); cut(); } } while (0)
#define SCAN2(T4) do { pin(hr); pin(hi); \
      float o_r[4], o_i[4]; \
      _Pragma("unroll") for (int e = 0; e < 4; e++) { \
        const int t = 4 * (T4) + e, ia = 4 * (t >> 1) + (t & 1), ib = ia + 2; \
        const float tr = fmaf(lc, hi, S[ia]), ti = fmaf(-lc, hr, S[ib]); \
        hr = fmaf(lr, hr, tr); hi = fmaf(lr, hi, ti); \
        o_r[e] = hr; o_i[e] = hi; } \
      hp[4 * (T4) + 0] = pack2(o_r[0], o_r[1]); hp[4 * (T4) + 1] = pack2(o_i[0], o_i[1]); \
      hp[4 * (T4) + 2] = pack2(o_r[2], o_r[3]); hp[4 * (T4) + 3] = pack2(o_i[2], o_i[3]); \
      pin(hp[4 * (T4)]); pin(hp[4 * (T4) + 1]); pin(hp[4 * (T4) + 2]); pin(hp[4 * (T4) + 3]); pin(hr); pin(hi); } while (0)
#define PUB_A() do { \
      float pr = __shfl_up_sync(~0u, hr, 1, 4); float pi = __shfl_up_sync(~0u, hi, 1, 4); \
      if (q >= 1) { hr += l32r * pr - l32i * pi; hi += l32r * pi + l32i * pr; } \
      pr = __shfl_up_sync(~0u, hr, 2, 4); pi = __shfl_up_sync(~0u, hi, 2, 4); \
      if (q >= 2) { hr += l64r * pr - l64i * pi; hi += l64r * pi + l64i * pr; } \
      if (q == 3) st_pkt2(agq + 4 * (NFC * 64), hr, hi, epoch); \
      } while (0)
#define QUAD_EXCL() do { er = __shfl_up_sync(~0u, hr, 1, 4); ei = __shfl_up_sync(~0u, hi, 1, 4); \
      if (q == 0) { er = 0.f; ei = 0.f; } pin(er); pin(ei); } while (0)
#define AG_LOAD() do { _Pragma("unroll") for (int j = 0; j < 4; j++) { \
        ag[j] = make_uint2(epoch & 1, 0); \
        if (m - 1 - q >= 4 * j) ag[j] = ld_pkt2(agq - 4 * j * (NFC * 64)); } } while (0)
#define AG_BAD() __any_sync(~0u, ((ag[0].x ^ epoch) | (ag[1].x ^ epoch) | (ag[2].x ^ epoch) | (ag[3].x ^ epoch)) & 1u)
#define CARRY_MATH() do { \
      cr = __uint_as_float(ag[3].x & ~1u); ci = __uint_as_float(ag[3].y); \
      _Pragma("unroll") for (int j = 2; j >= 0; j--) { \
        const float nr = l512r * cr - l512i * ci + __uint_as_float(ag[j].x & ~1u); const float ni = l512r * ci + l512i * cr + __uint_as_float(ag[j].y); \
        cr = nr; ci = ni; } \
      CMUL(cr, ci, cr, ci, w128r, w128i); \
      cr += __shfl_xor_sync(~0u, cr, 1); ci += __shfl_xor_sync(~0u, ci, 1); \
      cr += __shfl_xor_sync(~0u, cr, 2); ci += __shfl_xor_sync(~0u, ci, 2); \
      const float sr = er + w32r * cr - w32i * ci; const float si = ei + w32r * ci + w32i * cr; \
      hr = m00 * sr + m01 * si; hi = m10 * sr + m11 * si; } while (0)
#define CARRY() do { \
      if (AG_BAD()) { \
        int it = 0; \
        _Pragma("unroll 1") do { \
          _Pragma("unroll") for (int j = 0; j < 4; j++) { if (m - 1 - q >= 4 * j) ag[j] = ld_pkt2(agq - 4 * j * (NFC * 64)); } \
        } while (AG_BAD() && ++it < SPIN_LIMIT); } \
      CARRY_MATH(); \
      pin(hr); pin(hi); } while (0)
#define M0(k) MMA_A(0, k)
#define M1(k) MMA_A(1, k)
#define M2(k) MMA_A(2, k)
#define M3(k) MMA_A(3, k)
#define M4(k) MMA_A(4, k)
#define M5(k) MMA_A(5, k)
#define M6(k) MMA_A(6, k)
#define M7(k) MMA_A(7, k)
    KBLOCK(8, M0, {}, { reg_fence(S); SCAN1(0, 14); warp_arrive(bars + ZBAR); });
    KBLOCK(9, M1, SCAN1(14, 23), SCAN1(23, 32));
    KBLOCK(10, M2, PUB_A(), { QUAD_EXCL(); PREMUL(0, 5); });
    KBLOCK(11, M3, PREMUL(5, 11), PREMUL(11, 17));
    KBLOCK(12, M4, { AG_LOAD(); PREMUL(17, 22); }, PREMUL(22, 27));
    KBLOCK(13, M5, PREMUL(27, 32), CARRY());
    KBLOCK(14, M6, SCAN2(0), { SCAN2(1); SCAN2(2); });
    KBLOCK(15, M7, SCAN2(3), { SCAN2(4); mbar_wait(bars + GBAR, 0); });

    float Bc[48];
    uint32_t fa[32], fb[24];
#define MMA_B(kb, k) wgmma_ss_n96<0, 1, H128, H64>(Bc, dw + dlo(X_OFF + ((kb) ^ 2) * 16384 + (k) * 32, 16), db + dlo(RING_OFF + ((16 + (kb)) % NSLOT) * 16384 + (k) * 1024, 4096), ((kb) | (k)) != 0)
#define MDIST 2, 2, 3, 2, 2, 2, 2, 3,  3, 4, 3, 4, 3, 4, 3, 4,  6, 3, 3
#define MISH(I) (mish_run<mish_pos(I, MDIST), mish_pos((I) + 1, MDIST)>(ms, A, Bc, fa, fb))
#define M_(k) MMA_B(0, k)
    KBLOCK(16, M_, {
      const uint4 gr = lds128(sb + GROW_OFF + ch * 16);
      ms.baddr = sb + BIAS_OFF + 8 * q; ms.bn = lds64f(ms.baddr);
      SCAN2(5);
      g0 = __uint_as_float(gr.x); g1 = __uint_as_float(gr.y); ms.s[0] = __uint_as_float(gr.z); ms.s[1] = __uint_as_float(gr.w);
      ms.n[0] = -2.f * ms.s[0]; ms.n[1] = -2.f * ms.s[1]; pin(ms.n[0]); pin(ms.n[1]); }, { reg_fence(A); MISH(0); SCAN2(6); });
#undef M_
#define BBLOCK(KB, SIDE) do { \
      mbar_wait(bars + FULL + 8 * ((16 + (KB)) % NSLOT), ((16 + (KB)) / NSLOT) & 1); \
      wg_fence(); MMA_B(KB, 0); MMA_B(KB, 1); MMA_B(KB, 2); MMA_B(KB, 3); wg_commit(); wg_wait<1>(); RELEASE((15 + (KB)) % NSLOT); cut(); SIDE; cut(); } while (0)
#define PARK(J0, J1) do { _Pragma("unroll") for (int jj = (J0); jj < (J1); jj++) \
        asm volatile("stmatrix.sync.aligned.m8n8.x4.shared.b16 [%0], {%1,%2,%3,%4};" \
                     :: "r"((rowb ^ ((jj & 3) << 5)) + (jj >> 2) * 16384), \
                        "r"(hp[4 * jj]), "r"(hp[4 * jj + 1]), "r"(hp[4 * jj + 2]), "r"(hp[4 * jj + 3]) : "memory"); } while (0)
    const uint32_t rowb = sb + HT_OFF + (((l >> 3) & 1) * 64 + 8 * warp + (l & 7)) * 128 + (((l >> 4) ^ (l & 7)) << 4);
    BBLOCK(1, { MISH(1); SCAN2(7); });
    BBLOCK(2, MISH(2));
    BBLOCK(3, { MISH(3); mbar_wait(bars + EMPTY + 8 * (17 % NSLOT), (17 / NSLOT) & 1); PARK(0, 2); });
    BBLOCK(4, { MISH(4); PARK(2, 4); });
    BBLOCK(5, { MISH(5); PARK(4, 6); });
    BBLOCK(6, { PARK(6, 8); __syncwarp(); warp_arrive(bars + HBAR); MISH(6); });
    BBLOCK(7, MISH(7));

    float accL[32], accM[32], accH[32], sum[32];
    uint32_t pg[16];
    uint4 in[4], nb[4];
    const uint32_t tag = epoch;
    const uint32_t dht = db + ((HT_OFF + wg * 16384) >> 4);
    const uint32_t dbl = bars + DBAR + 8 * wg;
#define MMA_C(b, k)  wgmma_ss3_n192<1, 0, H128, H128>(accL, accM, accH, dht + dlo((4 * (b) + (k)) * 2048, 16), db + dlo(RING_OFF + (b) * 24576 + (k) * 32, 16), ((b) | (k)) != 0)
#define MMA_FA(b, k) wgmma_rs3_n192<1, H128>(accL, accM, accH, fa[16 * (b) + 4 * (k)], fa[16 * (b) + 4 * (k) + 1], fa[16 * (b) + 4 * (k) + 2], fa[16 * (b) + 4 * (k) + 3], db + dlo(RING_OFF + (2 + (b)) * 24576 + (k) * 2048, 8192), 1)
#define MMA_FB(b, k) wgmma_rs3_n192<1, H128>(accL, accM, accH, fb[12 * (b) + 4 * (k)], fb[12 * (b) + 4 * (k) + 1], fb[12 * (b) + 4 * (k) + 2], fb[12 * (b) + 4 * (k) + 3], db + dlo(RING_OFF + (b) * 24576 + (k) * 2048, 6144), 1)
#define PBLOCK4(B, MMA, HB, SIDE0, SIDE1) do { \
      mbar_wait(bars + FULL + 8 * (B), 0); \
      wg_fence(); MMA(HB, 0); MMA(HB, 1); wg_commit(); wg_wait<1>(); RELEASE(((B) + 5) % NSLOT); cut(); SIDE0; cut(); \
      wg_fence(); MMA(HB, 2); MMA(HB, 3); wg_commit(); cut(); SIDE1; cut(); } while (0)
#define PBLOCK3(B, HB, SIDE) do { \
      mbar_wait(bars + FULL + 8 * (B), 0); \
      wg_fence(); MMA_FB(HB, 0); MMA_FB(HB, 1); MMA_FB(HB, 2); wg_commit(); wg_wait<1>(); RELEASE((B) - 1); cut(); SIDE; cut(); } while (0)
#define GIVE(PK, U, I) give_pkt<I>(PK, xbr + (U) * 16384, dbr + 16 * (U))
#define TAKE(U) do { mbar_wait(dbl + 16 * (U), 0); take_piece(nb, xbl + (U) * 16384); } while (0)
#define STAGE(ACC, U) stage_sum(ACC, nb, xbl + (U) * 16384, tag)
#define FETCH(IN, U) recv_issue(IN, rbase + (U) * 1024)
#define SIGNAL(E) do { __syncwarp(); warp_arrive(dbl + XBAR - DBAR + 16 * ((E) - 1)); } while (0)
#define PACK(PK, ACC) pack_piece(PK, ACC)

    mbar_wait(bars + HRDY, 0);
    PBLOCK4(0, MMA_C, 0, {
      asm volatile("{\n.reg .pred p;\nelect.sync _|p, 0xffffffff;\n@p mbarrier.arrive.shared::cluster.b64 _, [%0];\n}" :: "r"(dbr - 8 * wg + RDY - DBAR) : "memory");
      reg_fence(Bc); MISH(8); }, MISH(9));
    PBLOCK4(1, MMA_C, 1, MISH(10), MISH(11));
    PBLOCK4(2, MMA_FA, 0, MISH(12), MISH(13));
    PBLOCK4(3, MMA_FA, 1, MISH(14), MISH(15));
    static_assert(mish_pos(8, MDIST) <= 32 && mish_pos(12, MDIST) >= 18 && mish_pos(14, MDIST) >= 34 && mish_pos(16, MDIST) >= 46 &&
                  mish_pos(17, MDIST) >= 50 && mish_pos(18, MDIST) >= 54 && mish_pos(19, MDIST) == 58, "Mish schedule");
    uint32_t hf[32];
#define LOAD_H(K0, K1) do { \
      const uint32_t ha = sb + HT_OFF + wg * 16384 + ((l >> 4) * 8 + (l & 7)) * 128 + (((2 * v + ((l >> 3) & 1)) ^ (l & 7)) << 4); \
      _Pragma("unroll") for (int k = (K0); k < (K1); k++) \
        asm volatile("ldmatrix.sync.aligned.m8n8.x4.trans.shared.b16 {%0,%1,%2,%3}, [%4];" \
                     : "=r"(hf[4 * k]), "=r"(hf[4 * k + 1]), "=r"(hf[4 * k + 2]), "=r"(hf[4 * k + 3]) : "r"(ha + k * 2048) : "memory"); } while (0)
    PBLOCK3(4, 0, MISH(16));
    mbar_wait(bars + FULL + 8 * 5, 0);
    wg_fence(); MMA_FB(1, 0); wg_commit(); cut(); MISH(17); cut();
    wg_fence(); MMA_FB(1, 1); wg_commit(); wg_wait<2>(); RELEASE(4); cut(); MISH(18); mbar_wait(bars + RDY, 0); cut();
    wg_fence(); MMA_FB(1, 2); wg_commit();
#define SKIP(JJ) do { pin(y[4 * (JJ)]); pin(y[4 * (JJ) + 1]); pin(y[4 * (JJ) + 2]); pin(y[4 * (JJ) + 3]); \
      acc0[8 * (JJ) + 0] = bf_lo(y[4 * (JJ)]);     acc0[8 * (JJ) + 1] = bf_hi(y[4 * (JJ)]); \
      acc0[8 * (JJ) + 2] = bf_lo(y[4 * (JJ) + 1]); acc0[8 * (JJ) + 3] = bf_hi(y[4 * (JJ) + 1]); \
      acc0[8 * (JJ) + 4] = bf_lo(y[4 * (JJ) + 2]); acc0[8 * (JJ) + 5] = bf_hi(y[4 * (JJ) + 2]); \
      acc0[8 * (JJ) + 6] = bf_lo(y[4 * (JJ) + 3]); acc0[8 * (JJ) + 7] = bf_hi(y[4 * (JJ) + 3]); \
      _Pragma("unroll") for (int j = 0; j < 8; j++) pin(acc0[8 * (JJ) + j]); } while (0)
#define STG_OFF(U) ((U) == 1 ? 0u - 49152u - o * 16384u : 49152u)
#define PUT(ACC, U) stage_piece(ACC, xbl + STG_OFF(U))

    float acc0[32], acc1[32];
#define MMA_FA0(ACC, O, k) wgmma_rs_n64<1, H128>(ACC, fa[4 * (k)], fa[4 * (k) + 1], fa[4 * (k) + 2], fa[4 * (k) + 3], db + dlo(RING_OFF + (O) * 16384 + (k) * 2048, 16), (k) != 0)
#define MMA_FA1(ACC, O, k) wgmma_rs_n64<1, H128>(ACC, fa[4 * (k)], fa[4 * (k) + 1], fa[4 * (k) + 2], fa[4 * (k) + 3], db + dlo(RING_OFF + (O) * 16384 + (k) * 2048, 16), 1)
#define MMA_FB1(ACC, O, k) wgmma_rs_n64<1, H128>(ACC, fb[4 * (k)], fb[4 * (k) + 1], fb[4 * (k) + 2], fb[4 * (k) + 3], db + dlo(RING_OFF + (O) * 16384 + (k) * 2048, 16), 1)
#define MMA_C1(ACC, O, k)  wgmma_rs_n64<0, H128>(ACC, hf[4 * (k)], hf[4 * (k) + 1], hf[4 * (k) + 2], hf[4 * (k) + 3], db + dlo(RING_OFF + (O) * 16384 + ((k) >> 2) * 8192 + ((k) & 3) * 32, 16), 1)
#define BURST(MMA, ACC, O, N) do { wg_fence(); _Pragma("unroll") for (int k = 0; k < (N); k++) MMA(ACC, O, k); wg_commit(); } while (0)
#define LAG_WAIT(ID) do { if (wg == 1) asm volatile("bar.sync %0, 256;" :: "n"(ID) : "memory"); } while (0)
#define LAG_SIG(ID) do { if (wg == 0) asm volatile("bar.arrive %0, 256;" :: "n"(ID) : "memory"); } while (0)
#define STEP(ID, B, PAR, MMA, ACC, N, SIDE) do { mbar_wait(bars + FULL + 8 * (B), PAR); if ((ID) > 0) LAG_WAIT((ID) & 7); \
      BURST(MMA, ACC, ((B) + 3) % NSLOT, N); if ((ID) > 0) LAG_SIG((ID) & 7); \
      wg_wait<1>(); warp_arrive(bars + ((ID) < 0 ? DONE : EMPTY + 8 * (((B) + 5) % NSLOT))); cut(); SIDE; cut(); } while (0)
#define MERGE(D, S_) do { _Pragma("unroll") for (int i = 0; i < 4; i++) { D[i].x = add2(D[i].x, S_[i].x); D[i].y = add2(D[i].y, S_[i].y); D[i].z = add2(D[i].z, S_[i].z); D[i].w = add2(D[i].w, S_[i].w); } } while (0)
#define CHECK(IN, U) recv_check(IN, rbase + (U) * 1024, tag)
#define GIVE2(U, I) do { GIVE(pg, U, I); GIVE(pg, U, (I) + 1); } while (0)
    STEP(1, 0, 1, MMA_FA0, acc0, 8, { reg_fence(accL); reg_fence(accM); reg_fence(accH); PACK(pg, accL); GIVE2(0, 0); PUT(accM, 1); });
    STEP(0, 1, 1, MMA_FB1, acc0, 6, { GIVE2(0, 2); SIGNAL(1); PUT(accH, 2); cut(); LOAD_H(0, 4); });
    STEP(0, 2, 1, MMA_FA0, acc1, 8, { LOAD_H(4, 8); SIGNAL(2); });
    STEP(0, 3, 1, MMA_C1, acc0, 8, TAKE(0));
    STEP(0, 4, 1, MMA_FB1, acc1, 6, { reg_fence(acc0); STAGE(acc0, 0); SIGNAL(3); });
    STEP(0, 5, 1, MMA_C1, acc1, 8, TAKE(1));
    STEP(2, 0, 0, MMA_FA0, acc0, 8, { reg_fence(acc1); STAGE(acc1, 1); SIGNAL(4); });
    STEP(0, 1, 0, MMA_FB1, acc0, 6, TAKE(2));
    STEP(0, 2, 0, MMA_C1, acc0, 8, LOAD_Y(DSK_OFF));
    const uint32_t oa = opaque32(sb + HT_OFF + warp * 2048 + r * 256 + ((((q >> 1) ^ (2 * r)) & 7) << 4) + (q & 1) * 8);
#define SKIP4() do { SKIP(0); SKIP(1); SKIP(2); SKIP(3); } while (0)
    uint4 i2[4];
    STEP(3, 3, 0, MMA_FA0, acc1, 8, { reg_fence(acc0); STAGE(acc0, 2); SIGNAL(5); });
    STEP(0, 4, 0, MMA_FB1, acc1, 6, { FETCH(in, 0); MUL_Y(); });
    STEP(0, 5, 0, MMA_C1, acc1, 8, SKIP4());
    STEP(0, 0, 1, MMA_FA1, acc0, 8, { CHECK(in, 0); FETCH(nb, 1); cut(); reg_fence(acc1); PACK(pg, acc1); GIVE2(3, 0); GIVE(pg, 3, 2); });
    STEP(0, 1, 1, MMA_FB1, acc0, 6, { FETCH(i2, 2); cut(); GIVE(pg, 3, 3); recv_add<true>(sum, in, g0, g1); });
    STEP(-1, 2, 1, MMA_C1, acc0, 8, { CHECK(nb, 1); CHECK(i2, 2); MERGE(i2, nb); TAKE(3); recv_add<false>(sum, i2, g0, g1); });
    recv_add<false>(sum, nb, g0, g1);
    wg_wait<0>();
    reg_fence(acc0);
    {
      const uint32_t wb = sb + HT_OFF + warp * 2048;
#pragma unroll
      for (int hf = 0; hf < 2; hf++) {
#pragma unroll
        for (int j = 4 * hf; j < 4 * hf + 4; j++) {
          asm volatile("st.shared.v2.f32 [%0], {%1,%2};" :: "r"((oa ^ ((j & 3) << 5)) + hf * 16384), "f"(fmaf(g0, acc0[4 * j], sum[4 * j])), "f"(fmaf(g0, acc0[4 * j + 1], sum[4 * j + 1])) : "memory");
          asm volatile("st.shared.v2.f32 [%0], {%1,%2};" :: "r"((oa ^ ((j & 3) << 5) ^ 16) + 128 + hf * 16384), "f"(fmaf(g1, acc0[4 * j + 2], sum[4 * j + 2])), "f"(fmaf(g1, acc0[4 * j + 3], sum[4 * j + 3])) : "memory");
        }
        asm volatile("{\n.reg .pred p;\nfence.proxy.async.shared::cta;\nbar.warp.sync 0xffffffff;\nelect.sync _|p, 0xffffffff;\n"
                     "@p cp.async.bulk.tensor.5d.global.shared::cta.bulk_group [%0, {%2, %3, %3, %3, %4}], [%1];\n}"
                     :: "l"(&tm.y), "r"(wb + hf * 16384), "r"(64 * f + 32 * hf), "r"(0), "r"(32 * m + warp) : "memory");
        cut();
      }
      asm volatile("cp.async.bulk.commit_group;\ncp.async.bulk.wait_group.read 0;" ::: "memory");
    }
    if (tid == 0) g_epoch[bid] = epoch;
  }
}

typedef CUresult (*EncodeFn)(CUtensorMap*, CUtensorMapDataType, cuuint32_t, void*, const cuuint64_t*, const cuuint64_t*,
                             const cuuint32_t*, const cuuint32_t*, CUtensorMapInterleave, CUtensorMapSwizzle,
                             CUtensorMapL2promotion, CUtensorMapFloatOOBfill);

bool encode(EncodeFn fn, CUtensorMap* map, const void* base, int rank, const cuuint64_t* dims, const cuuint64_t* strides,
            const cuuint32_t* box, CUtensorMapSwizzle sw, CUtensorMapDataType dt = CU_TENSOR_MAP_DATA_TYPE_BFLOAT16) {
  const cuuint32_t es[5] = {1, 1, 1, 1, 1};
  return fn(map, dt, rank, const_cast<void*>(base), dims, strides, box, es,
            CU_TENSOR_MAP_INTERLEAVE_NONE, sw,
            rank >= 4 ? CU_TENSOR_MAP_L2_PROMOTION_L2_128B : CU_TENSOR_MAP_L2_PROMOTION_L2_256B, CU_TENSOR_MAP_FLOAT_OOB_FILL_NONE) == CUDA_SUCCESS;
}

}

extern "C" void kernel_launch(void* const* d_in, const int* in_sizes, int n_in, void* d_out, int out_size) {
  (void)in_sizes; (void)n_in; (void)out_size;
  static EncodeFn fn = nullptr;
  static bool base1k = false;
  if (!fn) {
    void* sym = nullptr;
    cudaDriverEntryPointQueryResult qr;
    cudaGetDriverEntryPoint("cuTensorMapEncodeTiled", &sym, cudaEnableDefault, &qr);
    fn = (EncodeFn)sym;
    int dev = 0, reserved = 0;
    cudaFuncAttributes fa;
    cudaGetDevice(&dev);
    cudaDeviceGetAttribute(&reserved, cudaDevAttrReservedSharedMemoryPerBlock, dev);
    base1k = reserved == 1024 && cudaFuncGetAttributes(&fa, fused_kernel<true>) == cudaSuccess && fa.sharedSizeBytes == 0;
    cudaFuncSetAttribute(fused_kernel<true>, cudaFuncAttributeMaxDynamicSharedMemorySize, SMEM_BYTES);
    cudaFuncSetAttribute(fused_kernel<false>, cudaFuncAttributeMaxDynamicSharedMemorySize, SMEM_BYTES);
  }
  const char* x = (const char*)d_in[0];
  const char *bre = (const char*)d_in[3], *bim = (const char*)d_in[4];
  Params p;
  Maps tm;
  bool ok = fn != nullptr;
  p.swapB = bim < bre;
  if (ok) {
    {
      const cuuint64_t d[5] = {DM, 2, 4, 16, NMT}, s[4] = {DM * 2, 32 * DM * 2, 2 * DM * 2, 128 * DM * 2};
      const cuuint32_t b[5] = {64, 2, 4, 16, 1};
      ok &= encode(fn, &tm.x, x, 5, d, s, b, CU_TENSOR_MAP_SWIZZLE_128B);
    }
    {
      const cuuint64_t d[4] = {DM, 8, 2, 64}, s[3] = {DM * 2, (cuuint64_t)(p.swapB ? bre - bim : bim - bre), 8 * DM * 2};
      const cuuint32_t b[4] = {64, 8, 2, 8};
      ok &= encode(fn, &tm.b, p.swapB ? bim : bre, 4, d, s, b, CU_TENSOR_MAP_SWIZZLE_128B);
    }
    {
      const cuuint64_t d[3] = {64, DM, FF / 64}, s[2] = {FF * 2, 128};
      const cuuint32_t b[3] = {64, 64, 2};
      ok &= encode(fn, &tm.w1a, d_in[10], 3, d, s, b, CU_TENSOR_MAP_SWIZZLE_128B);
    }
    {
      const cuuint64_t d[3] = {32, DM, FF / 32}, s[2] = {FF * 2, 64};
      const cuuint32_t b[3] = {32, 64, 3};
      ok &= encode(fn, &tm.w1b, d_in[10], 3, d, s, b, CU_TENSOR_MAP_SWIZZLE_64B);
    }
    {
      const cuuint64_t d[2] = {DM, FF}, s[1] = {DM * 2};
      const cuuint32_t ba[2] = {64, 64}, bb[2] = {64, 48};
      ok &= encode(fn, &tm.w2a, d_in[12], 2, d, s, ba, CU_TENSOR_MAP_SWIZZLE_128B);
      ok &= encode(fn, &tm.w2b, d_in[12], 2, d, s, bb, CU_TENSOR_MAP_SWIZZLE_128B);
    }
    {
      const cuuint64_t d[2] = {DM, DM}, s[1] = {DM * 2};
      const cuuint32_t b[2] = {64, 64};
      ok &= encode(fn, &tm.cre, d_in[5], 2, d, s, b, CU_TENSOR_MAP_SWIZZLE_128B);
      ok &= encode(fn, &tm.cim, d_in[6], 2, d, s, b, CU_TENSOR_MAP_SWIZZLE_128B);
    }
    {
      const cuuint64_t d[5] = {DM, 2, 2, 4, 512}, s[4] = {2 * DM * 4, DM * 4, 32 * DM * 4, 4 * DM * 4};
      const cuuint32_t b[5] = {32, 2, 2, 4, 1};
      ok &= encode(fn, &tm.y, d_out, 5, d, s, b, CU_TENSOR_MAP_SWIZZLE_128B, CU_TENSOR_MAP_DATA_TYPE_FLOAT32);
    }
  }
  if (!ok) return;
  p.lam_re = (const __nv_bfloat16*)d_in[1]; p.lam_im = (const __nv_bfloat16*)d_in[2];
  p.log_dt = (const __nv_bfloat16*)d_in[7]; p.dskip = (const __nv_bfloat16*)d_in[8];
  p.b1 = (const __nv_bfloat16*)d_in[11]; p.gate = (const __nv_bfloat16*)d_in[13];
  p.xp = (const __nv_bfloat16*)x; p.b0 = (const __nv_bfloat16*)(p.swapB ? bim : bre); p.b1p = (const __nv_bfloat16*)(p.swapB ? bre : bim);
  if (base1k) fused_kernel<true><<<NMT * NFC, 384, SMEM_BYTES>>>(p, tm);
  else        fused_kernel<false><<<NMT * NFC, 384, SMEM_BYTES>>>(p, tm);
}
```
